```python
import torch

def _softmax(x, axis=-1):
    return torch.softmax(x, dim=axis)
def _gelu(x):
    return torch.nn.functional.gelu(x, approximate="tanh")
def _silu(x):
    return torch.nn.functional.silu(x)
def _sigmoid(x):
    return torch.sigmoid(x)
def _layernorm(x, axis=-1, eps=1e-5):
    m = x.mean(dim=axis, keepdim=True)
    v = x.var(dim=axis, keepdim=True, unbiased=False)
    return (x - m) / torch.sqrt(v + eps)
def _scatter_add(tgt, idx, src, axis=0):
    return tgt.clone().index_add_(axis, idx, src)
def _segment_sum(src, seg, n):
    out = torch.zeros((n,) + src.shape[1:], dtype=src.dtype)
    return out.index_add_(0, seg, src)
def _pad(x, pw):
    flat = tuple(v for pair in reversed(pw) for v in pair)
    return torch.nn.functional.pad(x, flat)

kernel_name = 'standalone__standard_2d_1d_3d_conv__vision'

def setup_inputs():

    _w = (lambda a: (lambda t: t.to(torch.bfloat16) if t.is_floating_point() else t)(torch.as_tensor(a)))
    H = W = 512
    C = 96
    K = 3
    return {
        "x": _w((lambda *s: torch.randn(*s, dtype=torch.bfloat16) * 0.05)(1, H, W, C)),
        "w": _w((lambda *s: torch.randn(*s, dtype=torch.bfloat16) * 0.05)(K, K, C, C)),
        "b": _w((lambda *s: torch.randn(*s, dtype=torch.bfloat16) * 0.05)(C)),
    }

def reference(x, w, b):
    B, H, W, Cin = x.shape
    K = w.shape[0]
    pl = (K - 1) // 2
    pr = K // 2
    xp = _pad(x, ((0, 0), (pl, pr), (pl, pr), (0, 0)))
    out = sum(
        torch.einsum('bhwc,cd->bhwd', xp[:, i:i+H, j:j+W, :], w[i, j])
        for i in range(K) for j in range(K)
    )
    return out + b[None, None, None, :]
```

```cpp
#include <cuda_runtime.h>
#include <cuda_bf16.h>
#include <cuda.h>
#include <stdint.h>

__device__ __forceinline__ void wgmma_n48(float* d, const uint32_t* a, uint64_t descB, int scaleD) {
  asm volatile("{\n.reg .pred p, q;\n"
    "setp.ne.b32 p, %29, 0;\n"
    "wgmma.mma_async.sync.aligned.m64n48k16.f32.bf16.bf16 "
    "{%0, %1, %2, %3, %4, %5, %6, %7, %8, %9, %10, %11, %12, %13, %14, %15, %16, %17, %18, %19, %20, %21, %22, %23}, "
    "{%24, %25, %26, %27}, %28, p, 1, 1, 1;\n}\n"
    : "+f"(d[0]), "+f"(d[1]), "+f"(d[2]), "+f"(d[3]), "+f"(d[4]), "+f"(d[5]), "+f"(d[6]), "+f"(d[7]),
      "+f"(d[8]), "+f"(d[9]), "+f"(d[10]), "+f"(d[11]), "+f"(d[12]), "+f"(d[13]), "+f"(d[14]), "+f"(d[15]),
      "+f"(d[16]), "+f"(d[17]), "+f"(d[18]), "+f"(d[19]), "+f"(d[20]), "+f"(d[21]), "+f"(d[22]), "+f"(d[23])
    : "r"(a[0]), "r"(a[1]), "r"(a[2]), "r"(a[3]), "l"(descB), "r"(scaleD));
}
__device__ __forceinline__ void wgmma_n48_p(float* d, const uint32_t* a, uint64_t descB, int scaleD, int pred) {
  asm volatile("{\n.reg .pred p, q;\n"
    "setp.ne.b32 p, %29, 0;\n"
    "setp.ne.b32 q, %30, 0;\n"
    "@q wgmma.mma_async.sync.aligned.m64n48k16.f32.bf16.bf16 "
    "{%0, %1, %2, %3, %4, %5, %6, %7, %8, %9, %10, %11, %12, %13, %14, %15, %16, %17, %18, %19, %20, %21, %22, %23}, "
    "{%24, %25, %26, %27}, %28, p, 1, 1, 1;\n}\n"
    : "+f"(d[0]), "+f"(d[1]), "+f"(d[2]), "+f"(d[3]), "+f"(d[4]), "+f"(d[5]), "+f"(d[6]), "+f"(d[7]),
      "+f"(d[8]), "+f"(d[9]), "+f"(d[10]), "+f"(d[11]), "+f"(d[12]), "+f"(d[13]), "+f"(d[14]), "+f"(d[15]),
      "+f"(d[16]), "+f"(d[17]), "+f"(d[18]), "+f"(d[19]), "+f"(d[20]), "+f"(d[21]), "+f"(d[22]), "+f"(d[23])
    : "r"(a[0]), "r"(a[1]), "r"(a[2]), "r"(a[3]), "l"(descB), "r"(scaleD), "r"(pred));
}
__device__ __forceinline__ void wgmma_n96(float* d, const uint32_t* a, uint64_t descB, int scaleD) {
  asm volatile("{\n.reg .pred p, q;\n"
    "setp.ne.b32 p, %53, 0;\n"
    "wgmma.mma_async.sync.aligned.m64n96k16.f32.bf16.bf16 "
    "{%0, %1, %2, %3, %4, %5, %6, %7, %8, %9, %10, %11, %12, %13, %14, %15, %16, %17, %18, %19, %20, %21, %22, %23, "
    "%24, %25, %26, %27, %28, %29, %30, %31, %32, %33, %34, %35, %36, %37, %38, %39, %40, %41, %42, %43, %44, %45, %46, %47}, "
    "{%48, %49, %50, %51}, %52, p, 1, 1, 1;\n}\n"
    : "+f"(d[0]), "+f"(d[1]), "+f"(d[2]), "+f"(d[3]), "+f"(d[4]), "+f"(d[5]), "+f"(d[6]), "+f"(d[7]),
      "+f"(d[8]), "+f"(d[9]), "+f"(d[10]), "+f"(d[11]), "+f"(d[12]), "+f"(d[13]), "+f"(d[14]), "+f"(d[15]),
      "+f"(d[16]), "+f"(d[17]), "+f"(d[18]), "+f"(d[19]), "+f"(d[20]), "+f"(d[21]), "+f"(d[22]), "+f"(d[23]),
      "+f"(d[24]), "+f"(d[25]), "+f"(d[26]), "+f"(d[27]), "+f"(d[28]), "+f"(d[29]), "+f"(d[30]), "+f"(d[31]),
      "+f"(d[32]), "+f"(d[33]), "+f"(d[34]), "+f"(d[35]), "+f"(d[36]), "+f"(d[37]), "+f"(d[38]), "+f"(d[39]),
      "+f"(d[40]), "+f"(d[41]), "+f"(d[42]), "+f"(d[43]), "+f"(d[44]), "+f"(d[45]), "+f"(d[46]), "+f"(d[47])
    : "r"(a[0]), "r"(a[1]), "r"(a[2]), "r"(a[3]), "l"(descB), "r"(scaleD));
}
__device__ __forceinline__ void wgmma_n144(float* d, const uint32_t* a, uint64_t descB, int scaleD) {
  asm volatile("{\n.reg .pred p, q;\n"
    "setp.ne.b32 p, %77, 0;\n"
    "wgmma.mma_async.sync.aligned.m64n144k16.f32.bf16.bf16 "
    "{%0, %1, %2, %3, %4, %5, %6, %7, %8, %9, %10, %11, %12, %13, %14, %15, %16, %17, %18, %19, %20, %21, %22, %23, "
    "%24, %25, %26, %27, %28, %29, %30, %31, %32, %33, %34, %35, %36, %37, %38, %39, %40, %41, %42, %43, %44, %45, %46, %47, "
    "%48, %49, %50, %51, %52, %53, %54, %55, %56, %57, %58, %59, %60, %61, %62, %63, %64, %65, %66, %67, %68, %69, %70, %71}, "
    "{%72, %73, %74, %75}, %76, p, 1, 1, 1;\n}\n"
    : "+f"(d[0]), "+f"(d[1]), "+f"(d[2]), "+f"(d[3]), "+f"(d[4]), "+f"(d[5]), "+f"(d[6]), "+f"(d[7]),
      "+f"(d[8]), "+f"(d[9]), "+f"(d[10]), "+f"(d[11]), "+f"(d[12]), "+f"(d[13]), "+f"(d[14]), "+f"(d[15]),
      "+f"(d[16]), "+f"(d[17]), "+f"(d[18]), "+f"(d[19]), "+f"(d[20]), "+f"(d[21]), "+f"(d[22]), "+f"(d[23]),
      "+f"(d[24]), "+f"(d[25]), "+f"(d[26]), "+f"(d[27]), "+f"(d[28]), "+f"(d[29]), "+f"(d[30]), "+f"(d[31]),
      "+f"(d[32]), "+f"(d[33]), "+f"(d[34]), "+f"(d[35]), "+f"(d[36]), "+f"(d[37]), "+f"(d[38]), "+f"(d[39]),
      "+f"(d[40]), "+f"(d[41]), "+f"(d[42]), "+f"(d[43]), "+f"(d[44]), "+f"(d[45]), "+f"(d[46]), "+f"(d[47]),
      "+f"(d[48]), "+f"(d[49]), "+f"(d[50]), "+f"(d[51]), "+f"(d[52]), "+f"(d[53]), "+f"(d[54]), "+f"(d[55]),
      "+f"(d[56]), "+f"(d[57]), "+f"(d[58]), "+f"(d[59]), "+f"(d[60]), "+f"(d[61]), "+f"(d[62]), "+f"(d[63]),
      "+f"(d[64]), "+f"(d[65]), "+f"(d[66]), "+f"(d[67]), "+f"(d[68]), "+f"(d[69]), "+f"(d[70]), "+f"(d[71])
    : "r"(a[0]), "r"(a[1]), "r"(a[2]), "r"(a[3]), "l"(descB), "r"(scaleD));
}

namespace {

constexpr int IMG = 512;
constexpr int CH = 96;
constexpr int NCTA = 128;
constexpr uint32_t U_TAP = 9216, U_POS = 3 * U_TAP;
constexpr uint32_t U_BYTES = 4 * U_POS;
constexpr uint32_t PLANE = 34 * 64;
constexpr uint32_t CHUNK = 4 * PLANE;
constexpr int NSLOT = 5;
constexpr uint32_t OPITCH = 112;
constexpr uint32_t OFF_RING = U_BYTES;
constexpr uint32_t OFF_STAGE = OFF_RING + 2 * NSLOT * CHUNK;
constexpr uint32_t OFF_BIAS = OFF_STAGE + 8 * 32 * OPITCH;
constexpr uint32_t OFF_BAR = OFF_BIAS + 256;
constexpr uint32_t SMEM_BYTES = OFF_BAR + 256;
constexpr uint32_t SMEM_BASE = 1024;
constexpr uint64_t DESC_U = (uint64_t)(SMEM_BASE >> 4) | ((uint64_t)(128 >> 4) << 16) | ((uint64_t)(1536 >> 4) << 32);
#define TOKEN_FROM 4
#define TOKEN_AT 1
#define NFL 2
#define LD_END 1
#define SPLIT_KIND 0
#define TOKEN 1
#define TOKEN_K 4
#define XPROMO 3
#define PF0 0
#define BLOOP 0
#define DEEP 0
#define LD_EF 0
#define ST_EF 0
#define PF_FROM 6
#define PF_CH 0
#define PF_DIST 1

__device__ __forceinline__ void wg_fence() { asm volatile("wgmma.fence.sync.aligned;" ::: "memory"); }
__device__ __forceinline__ void wg_commit() { asm volatile("wgmma.commit_group.sync.aligned;" ::: "memory"); }
template <int N> __device__ __forceinline__ void wg_wait() { asm volatile("wgmma.wait_group.sync.aligned %0;" ::"n"(N) : "memory"); }
__device__ __forceinline__ void ldsm4(uint32_t* r, uint32_t addr) {
  asm volatile("ldmatrix.sync.aligned.m8n8.x4.shared.b16 {%0,%1,%2,%3}, [%4];"
               : "=r"(r[0]), "=r"(r[1]), "=r"(r[2]), "=r"(r[3]) : "r"(addr) : "memory");
}
__device__ __forceinline__ void stsm4(uint32_t addr, uint32_t r0, uint32_t r1, uint32_t r2, uint32_t r3) {
  asm volatile("stmatrix.sync.aligned.m8n8.x4.shared.b16 [%0], {%1,%2,%3,%4};" ::"r"(addr), "r"(r0), "r"(r1), "r"(r2), "r"(r3) : "memory");
}
__device__ __forceinline__ uint32_t hadd2(uint32_t a, uint32_t b) {
  uint32_t r; asm volatile("add.rn.bf16x2 %0, %1, %2;" : "=r"(r) : "r"(a), "r"(b)); return r;
}
__device__ __forceinline__ uint32_t hsub2(uint32_t a, uint32_t b) {
  uint32_t r; asm volatile("sub.rn.bf16x2 %0, %1, %2;" : "=r"(r) : "r"(a), "r"(b)); return r;
}
__device__ __forceinline__ uint32_t pack2(float lo, float hi) {
  uint32_t r; asm("cvt.rn.bf16x2.f32 %0, %1, %2;" : "=r"(r) : "f"(hi), "f"(lo)); return r;
}
__device__ __forceinline__ float bf_lo(uint32_t v) { return __uint_as_float(v << 16); }
__device__ __forceinline__ float bf_hi(uint32_t v) { return __uint_as_float(v & 0xffff0000u); }
__device__ __forceinline__ void mbar_wait(uint32_t bar, uint32_t parity, int& budget) {
  asm volatile(
      "{\n.reg .pred p, q;\n"
      "AGAIN:\n"
      "mbarrier.try_wait.parity.shared::cta.b64 p, [%1], %2;\n"
      "sub.s32 %0, %0, 1;\n"
      "setp.gt.and.s32 q, %0, 0, !p;\n"
      "@q bra AGAIN;\n}\n" : "+r"(budget) : "r"(bar), "r"(parity) : "memory");
}
__device__ __forceinline__ void pin(float* a, int n) {
#pragma unroll
  for (int i = 0; i < n; i++) asm volatile("" : "+f"(a[i])::"memory");
}
#define TR(n)
#define TRP(n)
struct Ctx {
  uint32_t never;
  uint32_t a[4];
  uint32_t bias;
  uint32_t stg;
  uint64_t desc;
  uint64_t zero64;
  uint32_t full;
  uint32_t empty;
  uint32_t slot, soff, phase;
  bool lead;
  int arm;
  int wg;
};
struct Slot { uint32_t bar, off, par, ok; };
__device__ __forceinline__ void bound8(const uint32_t* u, const uint32_t* v, const Ctx& c) {
  asm volatile("{\n.reg .pred p;\nsetp.eq.u32 p, %8, 0;\n@p bra.uni SKIP;\n"
               "st.shared.v4.u32 [%9], {%0,%1,%2,%3};\nst.shared.v4.u32 [%9+16], {%4,%5,%6,%7};\nnanosleep.u32 1;\nSKIP:\n}\n"
               ::"r"(u[0]), "r"(u[1]), "r"(u[2]), "r"(u[3]), "r"(v[0]), "r"(v[1]), "r"(v[2]), "r"(v[3]), "r"(c.never), "r"(c.stg)
               : "memory");
}
__device__ __forceinline__ void anchor(const uint32_t* v, const Ctx& c) {
  asm volatile("{\n.reg .pred p;\nsetp.ne.u32 p, %4, 0;\n@p st.shared.v4.u32 [%5], {%0,%1,%2,%3};\n}\n"
               ::"r"(v[0]), "r"(v[1]), "r"(v[2]), "r"(v[3]), "r"(c.never), "r"(c.stg) : "memory");
}

__device__ __forceinline__ Slot peek(Ctx& c) {
  Slot s = {c.slot, c.soff, c.phase, 0};
  asm volatile("{\n.reg .pred p;\nmbarrier.test_wait.parity.shared::cta.b64 p, [%1], %2;\nselp.u32 %0, 1, 0, p;\n}\n"
               : "=r"(s.ok) : "r"(s.bar), "r"(s.par) : "memory");
  const bool wrap = s.off == (NSLOT - 1) * CHUNK;
  c.slot = wrap ? c.full : s.bar + 8;
  c.soff = wrap ? 0 : s.off + CHUNK;
  c.phase ^= wrap;
  asm volatile("" : "+r"(c.slot), "+r"(c.soff), "+r"(c.phase));
  return s;
}
__device__ __forceinline__ void confirm(const Ctx& c, Slot s) {
  asm volatile(
      "{\n.reg .pred p, q;\n.reg .s32 n;\n"
      "setp.ne.u32 p, %2, 0;\n"
      "@p bra.uni DONE;\n"
      "mov.s32 n, 1000000;\n"
      "AGAIN:\n"
      "mbarrier.try_wait.parity.shared::cta.b64 p, [%0], %1;\n"
      "sub.s32 n, n, 1;\n"
      "setp.gt.and.s32 q, n, 0, !p;\n"
      "@q bra.uni AGAIN;\n"
      "DONE:\n}\n" ::"r"(s.bar), "r"(s.par), "r"(s.ok) : "memory");
}
__device__ __forceinline__ void release(const Ctx& c, Slot s) {
  asm volatile("{\n.reg .pred p;\nsetp.ne.u32 p, %1, 0;\n@p mbarrier.arrive.shared::cluster.b64 _, [%0];\n}\n"
               ::"r"(s.bar ^ c.empty), "r"((uint32_t)c.lead) : "memory");
}
__device__ __forceinline__ void load_frag(uint32_t* d, const Ctx& c, Slot s, int odd) {
  ldsm4(d, c.a[odd] + s.off);
  ldsm4(d + 4, c.a[odd ^ 1] + s.off + 2 * PLANE);
  ldsm4(d + 8, c.a[2 + odd] + s.off);
}
__device__ __forceinline__ uint64_t refresh(uint64_t d, const Ctx& c) {
  uint64_t r;
  asm volatile("add.s64 %0, %1, %2;" : "=l"(r) : "l"(d), "l"(c.zero64));
  return r;
}
__device__ __forceinline__ void wait_weights(uint32_t bar) {
  asm volatile(
      "{\n.reg .pred p, q;\n.reg .s32 n;\n"
      "mov.s32 n, 1000000;\n"
      "AGAIN:\n"
      "mbarrier.try_wait.parity.shared::cta.b64 p, [%0], 0;\n"
      "sub.s32 n, n, 1;\n"
      "setp.gt.and.s32 q, n, 0, !p;\n"
      "@q bra.uni AGAIN;\n}\n" ::"r"(bar) : "memory");
}
__device__ __forceinline__ void token_wait(const Ctx& c) {
  asm volatile("{\n.reg .pred p;\nsetp.eq.s32 p, %0, 0;\n@p bar.sync 2, 256;\n@!p bar.sync 3, 256;\n}\n" ::"r"(c.wg) : "memory");
 }
__device__ __forceinline__ void token_pass(const Ctx& c) {
  asm volatile("{\n.reg .pred p;\nsetp.eq.s32 p, %0, 0;\n@p bar.arrive 3, 256;\n@!p bar.arrive 2, 256;\n}\n" ::"r"(c.wg) : "memory");
 }

__device__ __forceinline__ void stage_wait(const Ctx& c) {
  asm volatile("{\n.reg .pred p;\nsetp.eq.s32 p, %0, 0;\n@p bar.sync 9, 160;\n@!p bar.sync 10, 160;\n}\n" ::"r"(c.wg) : "memory");
}
__device__ __forceinline__ void stage_post(const Ctx& c) {
  asm volatile("{\n.reg .pred p;\nsetp.eq.s32 p, %0, 0;\n@p bar.arrive 7, 160;\n@!p bar.arrive 8, 160;\n}\n" ::"r"(c.wg) : "memory");
}

template <int PAR>
__device__ __forceinline__ void transform(const uint32_t* d, uint32_t* f0, uint32_t* f1, uint32_t* s0, uint32_t* s1) {
  uint32_t *v0 = PAR ? f0 : s0, *v3 = PAR ? f1 : s1, *v1 = PAR ? s0 : f0, *v2 = PAR ? s1 : f1;
#pragma unroll
  for (int h = 0; h < 2; h++) {
#pragma unroll
    for (int t = 0; t < 2; t++) {
      const uint32_t p0 = d[(t ? 2 : 8) + h], p1 = d[4 * t + h], p2 = d[4 * t + 2 + h], p3 = d[(t ? 10 : 4) + h];
      v0[2 * h + t] = hsub2(p0, p2);
      v1[2 * h + t] = hadd2(p1, p2);
      v2[2 * h + t] = hsub2(p2, p1);
      v3[2 * h + t] = hsub2(p3, p1);
    }
  }
}

__device__ __forceinline__ void load_bias(float* b, const Ctx& c) {
#pragma unroll
  for (int i = 0; i < 3; i++)
    asm volatile("ld.shared.v4.f32 {%0,%1,%2,%3}, [%4];"
                 : "=f"(b[4 * i]), "=f"(b[4 * i + 1]), "=f"(b[4 * i + 2]), "=f"(b[4 * i + 3]) : "r"(c.bias + 16 * i));
}
template <int LO, int HI>
__device__ __forceinline__ void mma_pair(float* A, const uint32_t* f, uint64_t desc) {
  if (LO && HI) wgmma_n96(A + 24, f, desc, 1);
  else if (LO) wgmma_n48(A + 24, f, desc, 1);
  else if (HI) wgmma_n48(A + 48, f, desc + (U_TAP >> 4), 1);
}

template <int PAR>
__device__ __forceinline__ void store_part(const float* X, const float* Z, const float* b, const Ctx& c, int j0, int j1) {
#pragma unroll
  for (int j = j0; j < j1; j++) {
    const float* x = X + 4 * j;
    const float* z = Z + 4 * j;
    if (PAR == 0) {
      const float b0 = b[2 * j], b1 = b[2 * j + 1];
      stsm4(c.stg + 16 * j, pack2(z[0] + b0, z[1] + b1), pack2(x[0] + b0, x[1] + b1), pack2(z[2] + b0, z[3] + b1),
            pack2(x[2] + b0, x[3] + b1));
    } else {
      stsm4(c.stg + 16 * j, pack2(fmaf(x[0], 0.5f, z[0]), fmaf(x[1], 0.5f, z[1])),
            pack2(fmaf(x[0], 0.5f, -z[0]), fmaf(x[1], 0.5f, -z[1])),
            pack2(fmaf(x[2], 0.5f, z[2]), fmaf(x[3], 0.5f, z[3])),
            pack2(fmaf(x[2], 0.5f, -z[2]), fmaf(x[3], 0.5f, -z[3])));
    }
  }
}

struct Regs {
  float X[72], Z[72];
  uint32_t s0[6][4], s1[6][4];
  uint32_t fl[4][4];
  uint32_t d0[12];
  Slot sl0, sl1;
};

template <int PAR, int MS, bool NEXT>
__device__ __forceinline__ void second_half(Regs& r, Ctx& c) {
  constexpr uint32_t D0 = ((PAR ? 1 : 0) * U_POS) >> 4, D1 = ((PAR ? 2 : 3) * U_POS) >> 4;
  constexpr uint32_t KS = 256 >> 4;
  constexpr uint32_t SA = (PAR ? 0 : 2 * U_TAP) >> 4, SP = (PAR ? U_TAP : 0) >> 4;
  constexpr int W = PAR ? 48 : 24, I = PAR ? 24 : 48;
  constexpr int SLO = MS & (PAR ? 2 : 1), SHI = MS & (PAR ? 1 : 2);
  float *X = r.X, *Z = r.Z;
  float* A0 = PAR ? X : Z;
  float* A1 = PAR ? Z : X;
  float b[12], t[24];
  if (NEXT) { r.sl0 = peek(c); r.sl1 = peek(c); }
  const uint64_t dS = refresh(c.desc, c);
  c.desc = refresh(dS, c);
  TR(7);
  wg_wait<0>();
  pin(X, 72); pin(Z, 72);
#pragma unroll
  for (int i = 0; i < 4; i++) anchor(r.fl[i], c);
  TR(0);
#pragma unroll
  for (int j = 0; j < 24; j++) {
    if (PAR == 0) {
      if (MS & 1) t[j] = fmaf(X[j], 0.5f, Z[j]);
      if (MS & 4) Z[j] = fmaf(X[W + j], 0.5f, Z[W + j]);
      if (MS & 1) X[W + j] = X[j] - t[j];
      if (MS & 4) X[j] = fmaf(Z[W + j], -2.0f, Z[j]);
    } else {
      if (MS & 1) t[j] = Z[j] + X[j];
      if (MS & 4) X[j] = Z[W + j] + X[W + j];
      if (MS & 1) Z[W + j] = fmaf(t[j], -0.5f, Z[j]);
      if (MS & 4) Z[j] = fmaf(X[j], 0.5f, -X[W + j]);
    }
  }
  if (MS & 4) {
    pin(X, 24); pin(Z, 24);
    TR(1);
    wg_fence();
  }
  if (PAR == 1 && (MS & 1)) load_bias(b, c);
  if (MS & 4) {
#pragma unroll
    for (int k = 0; k < 6; k++) {
      wgmma_n48(A0, r.s0[k], dS + (D0 + k * KS + SA), 1);
      wgmma_n48(A1, r.s1[k], dS + (D1 + k * KS + SA), 1);
      if (k == 2 && NEXT) { confirm(c, r.sl0); wg_fence(); }
    }
    wg_commit();
  } else if (NEXT) {
    confirm(c, r.sl0);
  }
  if (MS & 2) {
    pin(X + I, 24); pin(Z + I, 24);
#pragma unroll
    for (int j = 0; j < 24; j++) {
      if (PAR == 0) { Z[I + j] = fmaf(X[I + j], 0.5f, Z[I + j]); X[I + j] -= Z[I + j]; }
      else { X[I + j] += Z[I + j]; Z[I + j] = fmaf(X[I + j], -0.5f, Z[I + j]); }
    }
    pin(X + I, 24); pin(Z + I, 24);
  }
  if (MS & 1) {
    pin(t, 24);
#pragma unroll
    for (int j = 0; j < 24; j++) {
      if (PAR == 0) Z[W + j] = t[j] + __uint_as_float(c.never);
      else X[W + j] = fmaf(b[(j >> 2) * 2 + (j & 1)], 2.0f, t[j]);
    }
    pin(X + W, 24); pin(Z + W, 24);
  }
  if (MS & 3) wg_fence();
  if (PAR == 0 && (MS & 4)) load_bias(b, c);
  if (MS & 3) {
#pragma unroll
    for (int k = 0; k < 3; k++) {
      mma_pair<SLO, SHI>(A0, r.s0[k], dS + (D0 + k * KS + SP));
      mma_pair<SLO, SHI>(A1, r.s1[k], dS + (D1 + k * KS + SP));
    }
    wg_commit();
  }
  TR(2);
  if (MS & 4) {
    stage_wait(c);
    if (MS & 3) wg_wait<1>(); else wg_wait<0>();
    pin(X, 24); pin(Z, 24);
    store_part<PAR>(X, Z, b, c, 0, 6);
    stage_post(c);
  }
  TR(3);
  if (NEXT) load_frag(r.d0, c, r.sl0, 0);
  if (MS & 3) {
    wg_fence();
#pragma unroll
    for (int k = 3; k < 6; k++) {
      mma_pair<SLO, SHI>(A0, r.s0[k], dS + (D0 + k * KS + SP));
      mma_pair<SLO, SHI>(A1, r.s1[k], dS + (D1 + k * KS + SP));
    }
    wg_commit();
  }
}

template <int PAR, int MF>
__device__ __forceinline__ void first_half(Regs& r, Ctx& c) {
  constexpr uint32_t D0 = ((PAR ? 1 : 0) * U_POS) >> 4, D1 = ((PAR ? 2 : 3) * U_POS) >> 4;
  constexpr uint32_t KS = 256 >> 4;
  constexpr uint32_t FA = (PAR ? 2 * U_TAP : 0) >> 4, FP = (PAR ? 0 : U_TAP) >> 4;
  constexpr int FLO = MF & (PAR ? 4 : 2), FHI = MF & (PAR ? 2 : 4);
  constexpr bool TK = TOKEN && MF >= TOKEN_FROM;
  constexpr int NREL = (MF & 1) ? 3 : MF == 6 ? 1 : 0;
  float* A0 = PAR ? r.X : r.Z;
  float* A1 = PAR ? r.Z : r.X;
  uint32_t d1[12];
  Slot sl2;
  const uint64_t dF = refresh(c.desc, c);
  confirm(c, r.sl1);
  if (TK) token_wait(c);
  TR(4);
  load_frag(d1, c, r.sl0, 1);
#pragma unroll
  for (int k = 0; k < 6; k++) {
    uint32_t ft0[4], ft1[4];
    uint32_t* f0 = k >= 4 ? r.fl[2 * (5 - k)] : ft0;
    uint32_t* f1 = k >= 4 ? r.fl[2 * (5 - k) + 1] : ft1;
    uint32_t* d = (k & 1) ? d1 : r.d0;
    if (k == 0) sl2 = peek(c);
    if (k == 2) confirm(c, sl2);
    if (TK && k == TOKEN_K) token_pass(c);
    if (k == 0) { if (MF != 1) wg_wait<1>(); }
    else if (k <= DEEP) { if (k > 1) wg_wait<2>(); }
    else wg_wait<1>();
    transform<PAR ^ 1>(d, f0, f1, r.s0[k], r.s1[k]);
    const int keep = k > 0 ? 1 : MF == 7 ? c.never : 0;
    wg_fence();
    mma_pair<FLO, FHI>(A0, f0, dF + (D0 + k * KS + FP));
    if (MF & 1) wgmma_n48(A0, f0, dF + (D0 + k * KS + FA), keep);
    mma_pair<FLO, FHI>(A1, f1, dF + (D1 + k * KS + FP));
    if (MF & 1) wgmma_n48(A1, f1, dF + (D1 + k * KS + FA), keep);
    wg_commit();
    if (k == 1 && NREL > 0) release(c, r.sl0);
    if (k == 3 && NREL > 1) release(c, r.sl1);
    if (k < 4) load_frag(d, c, k < 2 ? r.sl1 : sl2, k & 1);
    if (k == 0) TR(5);
    if (k != 5) bound8(r.s0[k], r.s1[k], c);
  }
  if (NREL > 2) release(c, sl2);
  TR(6);
}

__device__ __forceinline__ void tma_chunk(uint32_t dst, const CUtensorMap* tm, int ch, int xq, int y, uint32_t bar) {
  asm volatile(
      "{\n.reg .pred p;\nelect.sync _|p, 0xffffffff;\n"
      "@p mbarrier.arrive.expect_tx.shared::cta.b64 _, [%6], %9;\n"
      "@p mbarrier.arrive.expect_tx.shared::cluster.b64 _, [%8], %9;\n"
      "@p cp.async.bulk.tensor.4d.shared::cluster.global.mbarrier::complete_tx::bytes.multicast::cluster "
      "[%0], [%1, {%2, %3, %4, %5}], [%6], %7;\n}\n"
      ::"r"(dst), "l"(tm), "r"(ch), "r"(xq), "r"(0), "r"(y), "r"(bar), "h"((uint16_t)3), "r"(bar ^ (1u << 24)), "n"(CHUNK)
      : "memory");
}

__device__ __forceinline__ void wino_w(uint32_t g0, uint32_t g1, uint32_t g2, uint32_t& u1, uint32_t& u2) {
  const float sl = bf_lo(g0) + bf_lo(g2), sh = bf_hi(g0) + bf_hi(g2);
  u1 = pack2(sl + bf_lo(g1), sh + bf_hi(g1));
  u2 = pack2((sl - bf_lo(g1)) * 0.5f, (sh - bf_hi(g1)) * 0.5f);
}
__device__ __forceinline__ void sts128(uint32_t a, uint4 v) {
  asm volatile("st.shared.v4.u32 [%0], {%1,%2,%3,%4};" ::"r"(a), "r"(v.x), "r"(v.y), "r"(v.z), "r"(v.w) : "memory");
}
__device__ __forceinline__ uint4 lds128(uint32_t a) {
  uint4 v;
  asm volatile("ld.shared.v4.u32 {%0,%1,%2,%3}, [%4];" : "=r"(v.x), "=r"(v.y), "=r"(v.z), "=r"(v.w) : "r"(a) : "memory");
  return v;
}
__device__ __forceinline__ uint32_t u_block(int pos, int ky) {
  return pos * U_POS + (pos == 0 || pos == 3 ? ky : 2 - ky) * U_TAP;
}
__device__ __forceinline__ uint32_t raw_zone(int ky, int pc) {
  return pc < 4 ? u_block(pc, ky) : OFF_STAGE + (2 * ky + pc - 8) * U_TAP;
}
template <bool MULTICAST>
__device__ __forceinline__ void load_raw(uint32_t sb, const __nv_bfloat16* w, int ky, uint32_t bar) {
#pragma unroll
  for (int pc = 0; pc < 6; pc++) {
    if (MULTICAST)
      asm volatile("{\n.reg .pred p;\nelect.sync _|p, 0xffffffff;\n"
                   "@p cp.async.bulk.shared::cluster.global.mbarrier::complete_tx::bytes.multicast::cluster [%0], [%1], %2, [%3], %4;\n}\n"
                   ::"r"(sb + raw_zone(ky, pc)), "l"(w + (ky * 6 + pc) * 48 * 96), "n"(U_TAP), "r"(bar), "h"((uint16_t)3) : "memory");
    else
      asm volatile("{\n.reg .pred p;\nelect.sync _|p, 0xffffffff;\n"
                   "@p cp.async.bulk.shared::cluster.global.mbarrier::complete_tx::bytes [%0], [%1], %2, [%3];\n}\n"
                   ::"r"(sb + raw_zone(ky, pc)), "l"(w + (ky * 6 + pc) * 48 * 96), "n"(U_TAP), "r"(bar) : "memory");
  }
}
__device__ __forceinline__ void prefetch_l2(const void* p, uint32_t bytes) {
  asm volatile("{\n.reg .pred p;\nelect.sync _|p, 0xffffffff;\n@p cp.async.bulk.prefetch.L2.global [%0], %1;\n}\n"
               ::"l"(p), "r"(bytes) : "memory");
}
__device__ __forceinline__ void prefetch_row(const __nv_bfloat16* x, int seg, int y) {
  const int x0 = max((seg & 3) * 128 - 4, 0), x1 = min((seg & 3) * 128 + 132, IMG);
  if (y >= 0) prefetch_l2(x + ((size_t)y * IMG + x0) * CH, (x1 - x0) * CH * 2);
}
__device__ __forceinline__ void bar_init(uint32_t bar, uint32_t count) {
  asm volatile("mbarrier.init.shared::cta.b64 [%0], %1;" ::"r"(bar), "r"(count) : "memory");
}

__global__ void __cluster_dims__(2, 1, 1) __launch_bounds__(384, 1)
conv_wino_kernel(const __grid_constant__ CUtensorMap tmx, const __grid_constant__ CUtensorMap tmo,
                 const __nv_bfloat16* __restrict__ x, const __nv_bfloat16* __restrict__ w,
                 const __nv_bfloat16* __restrict__ bias, uint64_t zero64, uint32_t never) {
  extern __shared__ __align__(1024) uint8_t smem_raw[];
  const uint32_t sb = (uint32_t)__cvta_generic_to_shared(smem_raw);
  if (sb != SMEM_BASE + ((blockIdx.x & 1) << 24)) __trap();
  TRP(0);
  const int tid = threadIdx.x, lane = tid & 31;
  const int warp = __shfl_sync(0xffffffff, tid >> 5, 0);
  const uint32_t rank = blockIdx.x & 1;
  const int cl = blockIdx.x >> 1;
  const uint32_t bar_full = sb + OFF_BAR;
  const uint32_t bar_empty = sb + OFF_BAR + 128;
  const int NROWS = 18 + never;

  const uint32_t bar_raw = sb + OFF_BAR + 192;
  const uint32_t bar_wrdy = sb + OFF_BAR + 224;
  if (warp == 8) {
    if (lane == 0) {
#pragma unroll
      for (int i = 0; i < 3; i++) bar_init(bar_raw + i * 8, 1);
#pragma unroll
      for (int i = 0; i < 3; i++)
        asm volatile("mbarrier.arrive.expect_tx.shared::cta.b64 _, [%0], %1;" ::"r"(bar_raw + i * 8), "n"(6 * U_TAP) : "memory");
    }
  } else if (warp == 9) {
    if (lane == 0) {
      asm volatile("prefetch.tensormap [%0];" ::"l"(&tmx) : "memory");
#pragma unroll
      for (int i = 0; i < NSLOT; i++) {
        bar_init(bar_full + i * 8, 1); bar_init(bar_full + 64 + i * 8, 1); bar_init(bar_empty + i * 8, 8);
      }
      bar_init(bar_wrdy, 5);
    }
  } else if (warp == 10) {
    if (blockIdx.x < 108) prefetch_l2(w + blockIdx.x * 768, 1536);
  }
  asm volatile("fence.mbarrier_init.release.cluster;" ::: "memory");
  __syncwarp();
  asm volatile("barrier.cluster.arrive.relaxed.aligned;" ::: "memory");
  if (warp == 8) {
    asm volatile("fence.proxy.async.shared::cta;" ::: "memory");
#pragma unroll 1
    for (int ky = 0; ky < 2; ky++) load_raw<false>(sb, w, ky, bar_raw + ky * 8);
  }
  asm volatile("barrier.cluster.wait.aligned;" ::: "memory");
  int budget = 1 << 22;

  if (warp < 8) {
    TRP(1);
    if (warp >= 4) asm volatile("bar.arrive 2, 256;" ::: "memory");
    {
      const int i = lane & 7;
      uint32_t src[5], dst[5];
#pragma unroll
      for (int it = 0; it < 5; it++) {
        const int u = (warp & 3) + 4 * it, q = u * 4 + (lane >> 3), rg = q / 6, j = (q + (i >> 1)) % 6;
        src[it] = sb + ((rg % 6) * 8 + i) * 192 + rank * 96 + j * 16;
        dst[it] = sb + j * 1536 + rg * 128 + i * 16;
        asm volatile("" : "+r"(src[it]), "+r"(dst[it]));
      }
#pragma unroll 1
      for (int ky = 0; ky < (warp >= 4 ? 3 : 2); ky++) {
        const bool lo = warp < 4 || ky == 2, hi = warp >= 4, last = hi && (warp & 3) < 2;
        uint4 g[5][3];
        mbar_wait(bar_raw + ky * 8, 0, budget);
        if (ky == 0) TRP(2);
#pragma unroll
        for (int it = 0; it < 5; it++) {
          if (it < 2 ? lo : it < 4 ? hi : last) {
            const bool lower = it < 2 || (it == 2 && (warp & 3) == 0);
#pragma unroll
            for (int kx = 0; kx < 3; kx++) g[it][kx] = lds128(src[it] + (lower ? raw_zone(ky, 2 * kx) : raw_zone(ky, 2 * kx + 1)));
          }
        }
        asm volatile("bar.sync %0, %1;" ::"r"(ky == 2 ? 5 : 1), "r"(ky == 2 ? 128 : 256) : "memory");
        if (ky == 0) TRP(3);
        if (ky == 1) TRP(5);
        if (ky == 1 && hi && lane < NSLOT)
          asm volatile("mbarrier.arrive.shared::cluster.b64 _, [%0];" ::"r"((bar_empty | (1u << 24)) + lane * 8) : "memory");
        __syncwarp();
#pragma unroll
        for (int it = 0; it < 5; it++) {
          if (it < 2 ? lo : it < 4 ? hi : last) {
            uint4 u1, u2;
            wino_w(g[it][0].x, g[it][1].x, g[it][2].x, u1.x, u2.x);
            wino_w(g[it][0].y, g[it][1].y, g[it][2].y, u1.y, u2.y);
            wino_w(g[it][0].z, g[it][1].z, g[it][2].z, u1.z, u2.z);
            wino_w(g[it][0].w, g[it][1].w, g[it][2].w, u1.w, u2.w);
            sts128(dst[it] + u_block(0, ky), g[it][0]);
            sts128(dst[it] + u_block(3, ky), g[it][2]);
            sts128(dst[it] + u_block(1, ky), u1);
            sts128(dst[it] + u_block(2, ky), u2);
          }
        }
        if (ky == 0) TRP(4);
        if (ky == 1) TRP(7);
        if (ky > 0) asm volatile("fence.proxy.async.shared::cta;" ::: "memory");
        if (ky == 1) {
          asm volatile("bar.sync 1, 256;" ::: "memory");
        } else if (ky == 2) {
          __syncwarp();
          if (lane == 0) asm volatile("mbarrier.arrive.shared::cta.b64 _, [%0];" ::"r"(bar_wrdy) : "memory");
          __syncwarp();
        }
      }
    }
    asm volatile("setmaxnreg.inc.sync.aligned.u32 240;");
    TRP(6);
    const int wg = warp >> 2, wq = warp & 3;
    Ctx c;
#pragma unroll
    for (int m = 0; m < 2; m++) {
      const int hi = lane >> 4, h = (lane >> 3) & 1, gg = lane & 7;
      const int xr = m == 0 ? hi : 3 - 3 * hi, xq = 8 * wq + gg + (m == 0 ? 1 : 2 * hi);
      const uint32_t ad = sb + OFF_RING + NSLOT * wg * CHUNK + xr * PLANE + xq * 64;
      c.a[2 * m] = ad + ((h ^ ((ad >> 7) & 3)) << 4);
      c.a[2 * m + 1] = c.a[2 * m] ^ 32;
      asm volatile("" : "+r"(c.a[2 * m]), "+r"(c.a[2 * m + 1]));
    }
    c.never = never;
    c.full = bar_full + wg * 64;
    asm volatile("mapa.shared::cluster.u32 %0, %1, %2;" : "=r"(c.empty) : "r"(bar_empty), "r"(wg));
    c.bias = sb + OFF_BIAS + (lane & 3) * 48 + never;
    c.stg = sb + OFF_STAGE + (wg * 128 + (lane >> 3) * 32 + wq * 8 + (lane & 7)) * OPITCH;
    c.empty ^= c.full;
    c.slot = c.full; c.soff = 0; c.phase = 0;
    c.wg = wg;
    c.desc = DESC_U;
    c.zero64 = zero64;
    c.lead = lane == 0;
    c.arm = wq == 0;
    Regs r;
#pragma unroll
    for (int i = 0; i < 72; i++) { r.X[i] = 0.f; r.Z[i] = 0.f; }
    r.sl0 = peek(c); r.sl1 = peek(c);
    confirm(c, r.sl0);
    load_frag(r.d0, c, r.sl0, 0);
    first_half<1, 1>(r, c);
    second_half<0, 1, true>(r, c);
    first_half<0, 3>(r, c);
    wait_weights(bar_wrdy);
    wg_wait<0>();
    pin(r.X, 72); pin(r.Z, 72);
#pragma unroll 1
    for (int i = 1;; i += 2) {
      if (__builtin_expect(i == 1, 0)) second_half<1, 3, true>(r, c);
      else second_half<1, 7, true>(r, c);
      if (__builtin_expect(i == NROWS - 3, 0)) first_half<1, 6>(r, c);
      else first_half<1, 7>(r, c);
      if (__builtin_expect(i >= NROWS - 3 + 2 * (int)never, 0)) break;
      if (__builtin_expect(never != 77, 1)) {
        second_half<0, 7, true>(r, c);
        first_half<0, 7>(r, c);
      }
    }
    second_half<0, 6, true>(r, c);
    first_half<0, 4>(r, c);
    second_half<1, 4, false>(r, c);
    if (wg == 0) token_wait(c);
  } else {
    asm volatile("setmaxnreg.dec.sync.aligned.u32 24;");
    if (warp == 8) asm volatile("bar.arrive 6, 64;" ::: "memory");
    if (warp == 10) {
      if (lane < 24) {
        const uint32_t v = *reinterpret_cast<const uint32_t*>(bias + rank * 48 + 2 * lane);
        asm volatile("st.shared.v2.f32 [%0], {%1, %2};" ::"r"(sb + OFF_BIAS + (lane & 3) * 48 + (lane >> 2) * 8),
                     "f"(bf_lo(v)), "f"(bf_hi(v)) : "memory");
      }
      __syncwarp();
      if (lane == 0) asm volatile("mbarrier.arrive.shared::cta.b64 _, [%0];" ::"r"(bar_wrdy) : "memory");
    }
    if (warp >= 10) {
      const int wg = warp - 10, seg = 2 * cl + wg;
#pragma unroll 1
      for (int i = 0; i < NROWS - 2; i++) {
        asm volatile("bar.arrive %0, 160;" ::"r"(9 + wg) : "memory");
        asm volatile("bar.sync %0, 160;" ::"r"(7 + wg) : "memory");
        asm volatile("fence.proxy.async.shared::cta;" ::: "memory");
        asm volatile(
            "{\n.reg .pred p;\nelect.sync _|p, 0xffffffff;\n"
            "@p cp.async.bulk.tensor.5d.global.shared::cta.bulk_group [%0, {%1, %2, %3, %1, %4}], [%5];\n}\n"
            ::"l"(&tmo), "r"(0), "r"(rank), "r"((seg & 3) * 32), "r"((seg >> 2) * 16 + i), "r"(sb + OFF_STAGE + wg * 128 * OPITCH)
            : "memory");
        asm volatile("cp.async.bulk.commit_group;" ::: "memory");
        asm volatile("cp.async.bulk.wait_group.read 0;" ::: "memory");
        __syncwarp();
      }
    }
    if (warp == 9) {
      const int seg_p = 2 * cl + rank;
      const int pxq = (seg_p & 3) * 32 - 1;
      int s = 0, ph = rank ^ 1, ch = 0, y = (seg_p >> 2) * 16 - 1;
      asm volatile("bar.sync 6, 64;" ::: "memory");
#pragma unroll 1
      for (int n = 0; n < 3 * NROWS; n++) {
        if (n == (rank ? 0 : 3)) {
          load_raw<false>(sb, w, 2, bar_raw + 16);
          if (rank) prefetch_row(x, seg_p, y);
        }
        if (ch == PF_CH && n >= 3 * PF_FROM && n - ch + 3 * PF_DIST < 3 * NROWS && y + PF_DIST < IMG) prefetch_row(x, seg_p, y + PF_DIST);
        mbar_wait(bar_empty + s * 8, ph, budget);
        tma_chunk(sb + OFF_RING + (NSLOT * rank + s) * CHUNK, &tmx, ch * 32, pxq, y, bar_full + rank * 64 + s * 8);
        if (++s == NSLOT) { s = 0; ph ^= 1; }
        if (++ch == 3) { ch = 0; y++; }
      }
    }
  }
}

typedef CUresult (*EncodeFn)(CUtensorMap*, CUtensorMapDataType, cuuint32_t, void*, const cuuint64_t*, const cuuint64_t*,
                             const cuuint32_t*, const cuuint32_t*, CUtensorMapInterleave, CUtensorMapSwizzle,
                             CUtensorMapL2promotion, CUtensorMapFloatOOBfill);
constexpr uint32_t SMEM_LAUNCH = SMEM_BYTES;

}

extern "C" void kernel_launch(void* const* d_in, const int* in_sizes, int n_in, void* d_out, int out_size) {
  (void)in_sizes; (void)n_in; (void)out_size;
  static EncodeFn encode = nullptr;
  if (!encode) {
    void* fn = nullptr;
    cudaDriverEntryPointQueryResult qr;
    cudaGetDriverEntryPoint("cuTensorMapEncodeTiled", &fn, cudaEnableDefault, &qr);
    encode = (EncodeFn)fn;
    cudaFuncSetAttribute(conv_wino_kernel, cudaFuncAttributeMaxDynamicSharedMemorySize, SMEM_LAUNCH);
  }
  CUtensorMap tmx, tmo;
  const cuuint32_t es[5] = {1, 1, 1, 1, 1};
  {
    const cuuint64_t dims[4] = {CH, IMG / 4, 4, IMG};
    const cuuint64_t strides[3] = {4 * CH * 2, CH * 2, (cuuint64_t)IMG * CH * 2};
    const cuuint32_t box[4] = {32, 34, 4, 1};
    encode(&tmx, CU_TENSOR_MAP_DATA_TYPE_BFLOAT16, 4, d_in[0], dims, strides, box, es, CU_TENSOR_MAP_INTERLEAVE_NONE,
           CU_TENSOR_MAP_SWIZZLE_64B, (CUtensorMapL2promotion)XPROMO, CU_TENSOR_MAP_FLOAT_OOB_FILL_NONE);
  }
  {
    const cuuint64_t dims[5] = {48, 2, IMG / 4, 4, IMG};
    const cuuint64_t strides[4] = {96, 4 * CH * 2, CH * 2, (cuuint64_t)IMG * CH * 2};
    const cuuint32_t box[5] = {OPITCH / 2, 1, 32, 4, 1};
    encode(&tmo, CU_TENSOR_MAP_DATA_TYPE_BFLOAT16, 5, d_out, dims, strides, box, es, CU_TENSOR_MAP_INTERLEAVE_NONE,
           CU_TENSOR_MAP_SWIZZLE_NONE, CU_TENSOR_MAP_L2_PROMOTION_NONE, CU_TENSOR_MAP_FLOAT_OOB_FILL_NONE);
  }
  conv_wino_kernel<<<NCTA, 384, SMEM_LAUNCH>>>(tmx, tmo, (const __nv_bfloat16*)d_in[0], (const __nv_bfloat16*)d_in[1],
                                              (const __nv_bfloat16*)d_in[2], 0ull, 0u);
}
```

```cpp
#include <cuda_runtime.h>
#include <cuda_bf16.h>
#include <cuda.h>
#include <stdint.h>

__device__ __forceinline__ void wgmma_n48(float* d, const uint32_t* a, uint64_t descB, int scaleD) {
  asm volatile("{\n.reg .pred p;\n"
    "setp.ne.b32 p, %29, 0;\n"
    "wgmma.mma_async.sync.aligned.m64n48k16.f32.bf16.bf16 "
    "{%0, %1, %2, %3, %4, %5, %6, %7, %8, %9, %10, %11, %12, %13, %14, %15, %16, %17, %18, %19, %20, %21, %22, %23}, "
    "{%24, %25, %26, %27}, %28, p, 1, 1, 1;\n}\n"
    : "+f"(d[0]), "+f"(d[1]), "+f"(d[2]), "+f"(d[3]), "+f"(d[4]), "+f"(d[5]), "+f"(d[6]), "+f"(d[7]),
      "+f"(d[8]), "+f"(d[9]), "+f"(d[10]), "+f"(d[11]), "+f"(d[12]), "+f"(d[13]), "+f"(d[14]), "+f"(d[15]),
      "+f"(d[16]), "+f"(d[17]), "+f"(d[18]), "+f"(d[19]), "+f"(d[20]), "+f"(d[21]), "+f"(d[22]), "+f"(d[23])
    : "r"(a[0]), "r"(a[1]), "r"(a[2]), "r"(a[3]), "l"(descB), "r"(scaleD));
}
__device__ __forceinline__ void wgmma_n96(float* d, const uint32_t* a, uint64_t descB, int scaleD) {
  asm volatile("{\n.reg .pred p;\n"
    "setp.ne.b32 p, %53, 0;\n"
    "wgmma.mma_async.sync.aligned.m64n96k16.f32.bf16.bf16 "
    "{%0, %1, %2, %3, %4, %5, %6, %7, %8, %9, %10, %11, %12, %13, %14, %15, %16, %17, %18, %19, %20, %21, %22, %23, "
    "%24, %25, %26, %27, %28, %29, %30, %31, %32, %33, %34, %35, %36, %37, %38, %39, %40, %41, %42, %43, %44, %45, %46, %47}, "
    "{%48, %49, %50, %51}, %52, p, 1, 1, 1;\n}\n"
    : "+f"(d[0]), "+f"(d[1]), "+f"(d[2]), "+f"(d[3]), "+f"(d[4]), "+f"(d[5]), "+f"(d[6]), "+f"(d[7]),
      "+f"(d[8]), "+f"(d[9]), "+f"(d[10]), "+f"(d[11]), "+f"(d[12]), "+f"(d[13]), "+f"(d[14]), "+f"(d[15]),
      "+f"(d[16]), "+f"(d[17]), "+f"(d[18]), "+f"(d[19]), "+f"(d[20]), "+f"(d[21]), "+f"(d[22]), "+f"(d[23]),
      "+f"(d[24]), "+f"(d[25]), "+f"(d[26]), "+f"(d[27]), "+f"(d[28]), "+f"(d[29]), "+f"(d[30]), "+f"(d[31]),
      "+f"(d[32]), "+f"(d[33]), "+f"(d[34]), "+f"(d[35]), "+f"(d[36]), "+f"(d[37]), "+f"(d[38]), "+f"(d[39]),
      "+f"(d[40]), "+f"(d[41]), "+f"(d[42]), "+f"(d[43]), "+f"(d[44]), "+f"(d[45]), "+f"(d[46]), "+f"(d[47])
    : "r"(a[0]), "r"(a[1]), "r"(a[2]), "r"(a[3]), "l"(descB), "r"(scaleD));
}

namespace {

constexpr int IMG = 512;
constexpr int CH = 96;
constexpr int NCTA = 132;
constexpr uint32_t U_TAP = 9216, U_POS = 3 * U_TAP;
constexpr uint32_t PLANE = 34 * 64;
constexpr uint32_t CHUNK = 4 * PLANE;
constexpr int NSLOT = 5;
constexpr uint32_t STAGE = 128 * 128;
constexpr uint32_t OFF_RING = 4 * U_POS;
constexpr uint32_t OFF_STAGE = OFF_RING + 2 * NSLOT * CHUNK;
constexpr uint32_t OFF_BIAS = OFF_STAGE + 2 * STAGE;
constexpr uint32_t OFF_BAR = OFF_BIAS + 256;
constexpr uint32_t SMEM_BYTES = OFF_BAR + 256;
constexpr uint32_t SMEM_BASE = 1024;
constexpr uint64_t DESC_U = (uint64_t)(SMEM_BASE >> 4) | ((uint64_t)(128 >> 4) << 16) | ((uint64_t)(1536 >> 4) << 32);
constexpr uint32_t B_FULL = 0;
constexpr uint32_t B_EMPTY = 64;
constexpr uint32_t B_HAND = 96;
constexpr uint32_t B_RAW = 104;
constexpr uint32_t B_WRDY = 128;
constexpr int PF_FROM = 6;

__device__ __forceinline__ void wg_fence() { asm volatile("wgmma.fence.sync.aligned;" ::: "memory"); }
__device__ __forceinline__ void wg_commit() { asm volatile("wgmma.commit_group.sync.aligned;" ::: "memory"); }
template <int N> __device__ __forceinline__ void wg_wait() { asm volatile("wgmma.wait_group.sync.aligned %0;" ::"n"(N) : "memory"); }
__device__ __forceinline__ void ldsm4(uint32_t* r, uint32_t addr) {
  asm volatile("ldmatrix.sync.aligned.m8n8.x4.shared.b16 {%0,%1,%2,%3}, [%4];"
               : "=r"(r[0]), "=r"(r[1]), "=r"(r[2]), "=r"(r[3]) : "r"(addr) : "memory");
}
__device__ __forceinline__ void stsm4(uint32_t addr, uint32_t r0, uint32_t r1, uint32_t r2, uint32_t r3) {
  asm volatile("stmatrix.sync.aligned.m8n8.x4.shared.b16 [%0], {%1,%2,%3,%4};" ::"r"(addr), "r"(r0), "r"(r1), "r"(r2), "r"(r3) : "memory");
}
__device__ __forceinline__ uint32_t hadd2(uint32_t a, uint32_t b) {
  uint32_t r; asm volatile("add.rn.bf16x2 %0, %1, %2;" : "=r"(r) : "r"(a), "r"(b)); return r;
}
__device__ __forceinline__ uint32_t hsub2(uint32_t a, uint32_t b) {
  uint32_t r; asm volatile("sub.rn.bf16x2 %0, %1, %2;" : "=r"(r) : "r"(a), "r"(b)); return r;
}
__device__ __forceinline__ uint32_t pack2(float lo, float hi) {
  uint32_t r; asm("cvt.rn.bf16x2.f32 %0, %1, %2;" : "=r"(r) : "f"(hi), "f"(lo)); return r;
}
__device__ __forceinline__ float bf_lo(uint32_t v) { return __uint_as_float(v << 16); }
__device__ __forceinline__ float bf_hi(uint32_t v) { return __uint_as_float(v & 0xffff0000u); }
__device__ __forceinline__ void pin(float* a, int n) {
#pragma unroll
  for (int i = 0; i < n; i++) asm volatile("" : "+f"(a[i])::"memory");
}
__device__ __forceinline__ void mbar_wait(uint32_t bar, uint32_t parity) {
  asm volatile(
      "{\n.reg .pred p, q;\n.reg .s32 n;\n"
      "mov.s32 n, 1000000;\n"
      "AGAIN:\n"
      "mbarrier.try_wait.parity.shared::cta.b64 p, [%0], %1;\n"
      "sub.s32 n, n, 1;\n"
      "setp.gt.and.s32 q, n, 0, !p;\n"
      "@q bra.uni AGAIN;\n}\n" ::"r"(bar), "r"(parity) : "memory");
}
__device__ __forceinline__ uint32_t peek(uint32_t bar, uint32_t parity) {
  uint32_t ok;
  asm volatile("{\n.reg .pred p;\nmbarrier.test_wait.parity.shared::cta.b64 p, [%1], %2;\nselp.u32 %0, 1, 0, p;\n}\n"
               : "=r"(ok) : "r"(bar), "r"(parity) : "memory");
  return ok;
}
__device__ __forceinline__ void confirm(uint32_t ok, uint32_t bar, uint32_t parity) {
  asm volatile(
      "{\n.reg .pred p, q;\n.reg .s32 n;\n"
      "setp.ne.u32 p, %2, 0;\n"
      "@p bra.uni DONE;\n"
      "mov.s32 n, 1000000;\n"
      "AGAIN:\n"
      "mbarrier.try_wait.parity.shared::cta.b64 p, [%0], %1;\n"
      "sub.s32 n, n, 1;\n"
      "setp.gt.and.s32 q, n, 0, !p;\n"
      "@q bra.uni AGAIN;\n"
      "DONE:\n}\n" ::"r"(bar), "r"(parity), "r"(ok) : "memory");
}

__device__ __forceinline__ int seg_rows(int cl, int wg) { return cl < 64 ? 16 - wg : 16; }
__device__ __forceinline__ int seg_strip(int cl, int wg) { return (cl & 1) * 2 + (((cl >> 1) & 1) ^ wg); }
__device__ __forceinline__ int seg_y0(int cl, int wg) { return (cl >> 2) * 31 + ((cl & 2) ? 15 + wg : 0); }
__device__ __forceinline__ uint32_t alt_stage(int wg) { return OFF_RING + wg * (NSLOT + 1) * CHUNK; }

struct Ctx {
  uint32_t a[4];
  uint32_t stg;
  bool lead;
  uint32_t never;
  uint64_t zero64;
  uint64_t desc;
  uint32_t bias;
  uint32_t full;
  uint32_t empty;
  uint32_t wready;
  uint32_t o0, o1, o2;
  uint32_t row;
  bool wg1;
  bool live;
};

__device__ __forceinline__ void bound8(const uint32_t* u, const uint32_t* v, const Ctx& c) {
  asm volatile("{\n.reg .pred p;\nsetp.ne.u32 p, %8, 0;\n@p bra.uni SKIP;\n"
               "st.shared.v4.u32 [%9], {%0,%1,%2,%3};\nst.shared.v4.u32 [%9+16], {%4,%5,%6,%7};\nnanosleep.u32 1;\nSKIP:\n}\n"
               ::"r"(u[0]), "r"(u[1]), "r"(u[2]), "r"(u[3]), "r"(v[0]), "r"(v[1]), "r"(v[2]), "r"(v[3]), "r"((uint32_t)c.live), "r"(c.a[0])
               : "memory");
}
__device__ __forceinline__ void anchor(const uint32_t* v, const Ctx& c) {
  asm volatile("{\n.reg .pred p;\nsetp.eq.u32 p, %4, 0;\n@p st.shared.v4.u32 [%5], {%0,%1,%2,%3};\n}\n"
               ::"r"(v[0]), "r"(v[1]), "r"(v[2]), "r"(v[3]), "r"((uint32_t)c.live), "r"(c.a[0]) : "memory");
}
__device__ __forceinline__ uint64_t refresh(uint64_t d, const Ctx& c) {
  uint64_t r;
  asm volatile("add.s64 %0, %1, %2;" : "=l"(r) : "l"(d), "l"(c.zero64));
  return r;
}
__device__ __forceinline__ void release(const Ctx& c, uint32_t off) {
  asm volatile("{\n.reg .pred p;\nsetp.ne.u32 p, %1, 0;\n@p mbarrier.arrive.shared::cluster.b64 _, [%0];\n}\n"
               ::"r"(c.empty + off), "r"((uint32_t)c.lead) : "memory");
}
__device__ __forceinline__ uint32_t next_slot(uint32_t o) { return o == (NSLOT - 1) * CHUNK ? 0 : o + CHUNK; }
__device__ __forceinline__ void advance(Ctx& c) {
  const uint32_t n0 = next_slot(c.o2);
  c.o2 = c.o0; c.o0 = n0; c.o1 = next_slot(n0);
  c.row++;
  asm volatile("" : "+r"(c.o0), "+r"(c.o1), "+r"(c.o2), "+r"(c.row));
}
#define WG_BAR(op, id0, id1, n) \
  asm volatile("{\n.reg .pred p;\nsetp.ne.u32 p, %0, 0;\n@!p bar." op " " #id0 ", " #n ";\n@p bar." op " " #id1 ", " #n ";\n}\n" \
               ::"r"((uint32_t)c.wg1) : "memory")
__device__ __forceinline__ void token_wait(const Ctx& c) { WG_BAR("sync", 2, 3, 256); }
__device__ __forceinline__ void token_pass(const Ctx& c) { WG_BAR("arrive", 3, 2, 256); }
__device__ __forceinline__ void stage_wait(const Ctx& c) { WG_BAR("sync", 8, 9, 160); }
__device__ __forceinline__ void stage_post(const Ctx& c) { WG_BAR("arrive", 14, 15, 160); }

__device__ __forceinline__ void load_frag(uint32_t* d, const Ctx& c, uint32_t off, int odd) {
  ldsm4(d, c.a[odd] + off);
  ldsm4(d + 4, c.a[odd ^ 1] + off + 2 * PLANE);
  ldsm4(d + 8, c.a[2 + odd] + off);
}
__device__ __forceinline__ void transform(const uint32_t* d, uint32_t* v0, uint32_t* v1, uint32_t* v2, uint32_t* v3) {
#pragma unroll
  for (int h = 0; h < 2; h++) {
#pragma unroll
    for (int t = 0; t < 2; t++) {
      const uint32_t p0 = d[(t ? 2 : 8) + h], p1 = d[4 * t + h], p2 = d[4 * t + 2 + h], p3 = d[(t ? 10 : 4) + h];
      v0[2 * h + t] = hsub2(p0, p2);
      v1[2 * h + t] = hadd2(p1, p2);
      v2[2 * h + t] = hsub2(p2, p1);
      v3[2 * h + t] = hsub2(p3, p1);
    }
  }
}
__device__ __forceinline__ void load_bias(float* b, const Ctx& c) {
  uint32_t q;
  asm volatile("and.b32 %0, %1, 0xC0;" : "=r"(q) : "r"(c.a[2]));
#pragma unroll
  for (int i = 0; i < 3; i++)
    asm volatile("ld.shared.v4.f32 {%0,%1,%2,%3}, [%4];"
                 : "=f"(b[4 * i]), "=f"(b[4 * i + 1]), "=f"(b[4 * i + 2]), "=f"(b[4 * i + 3]) : "r"(q + c.bias + 16 * i));
}
template <int LO, int HI, int HOFF>
__device__ __forceinline__ void mma_pair(float* A, const uint32_t* f, uint64_t desc) {
  if (LO && HI) wgmma_n96(A + 24, f, desc, 1);
  else if (LO) wgmma_n48(A + 24, f, desc, 1);
  else if (HI) wgmma_n48(A + HOFF, f, desc + (U_TAP >> 4), 1);
}
__device__ __forceinline__ void stage_cols(const Ctx& c, int j, const float* y0, const float* y1) {
  uint32_t a = c.stg;
  if (j) asm volatile("xor.b32 %0, %1, %2;" : "=r"(a) : "r"(c.stg), "r"(16 * j));
  stsm4(a, pack2(y0[0], y0[1]), pack2(y1[0], y1[1]), pack2(y0[2], y0[3]), pack2(y1[2], y1[3]));
}
template <int PAR>
__device__ __forceinline__ void store_part(const float* X, const float* Z, const Ctx& c, int j0, int j1) {
#pragma unroll
  for (int j = j0; j < j1; j++) {
    if (PAR == 0) {
      stage_cols(c, j, Z + 4 * j, X + 4 * j);
    } else {
      float y0[4], y1[4];
#pragma unroll
      for (int e = 0; e < 4; e++) { y0[e] = fmaf(X[4 * j + e], 0.5f, Z[4 * j + e]); y1[e] = fmaf(X[4 * j + e], 0.5f, -Z[4 * j + e]); }
      stage_cols(c, j, y0, y1);
    }
  }
}

struct Regs {
  float X[72], Z[72];
  uint32_t s0[6][4], s1[6][4];
  uint32_t fl[4][4];
  uint32_t d0[12];
};

template <int PAR, int MS, bool NEXT = true>
__device__ __forceinline__ void second_half(Regs& r, Ctx& c) {
  constexpr uint32_t D0 = ((PAR ? 1 : 0) * U_POS) >> 4, D1 = ((PAR ? 2 : 3) * U_POS) >> 4;
  constexpr uint32_t KS = 256 >> 4;
  constexpr uint32_t SA = (PAR ? 0 : 2 * U_TAP) >> 4, SP = (PAR ? U_TAP : 0) >> 4;
  constexpr int W = PAR ? 48 : 24, I = PAR ? 24 : 48;
  constexpr int SLO = MS & (PAR ? 2 : 1), SHI = MS & (PAR ? 1 : 2);
  float *X = r.X, *Z = r.Z;
  float* A0 = PAR ? X : Z;
  float* A1 = PAR ? Z : X;
  constexpr int ES = PAR ? 4 : 3;
  float b[12], t[24];
  uint32_t ok = 0;
  if (NEXT) { advance(c); ok = peek(c.full + PAR * 8, c.row >> 1); }
  const uint64_t dS = refresh(c.desc, c);
  c.desc = refresh(dS, c);
  wg_wait<0>();
  pin(X, 72); pin(Z, 72);
#pragma unroll
  for (int i = 0; i < 4; i++) anchor(r.fl[i], c);
#pragma unroll
  for (int j = 0; j < 24; j++) {
    if (PAR == 0) {
      if (MS & 1) t[j] = fmaf(X[j], 0.5f, Z[j]);
      if (MS & 4) Z[j] = fmaf(X[W + j], 0.5f, Z[W + j]);
      if (MS & 1) X[W + j] = X[j] - t[j];
      if (MS & 4) X[j] = fmaf(Z[W + j], -2.0f, Z[j]);
    } else {
      if (MS & 1) t[j] = Z[j] + X[j];
      if (MS & 4) X[j] = Z[W + j] + X[W + j];
      if (MS & 1) Z[W + j] = fmaf(t[j], -0.5f, Z[j]);
      if (MS & 4) Z[j] = fmaf(X[j], 0.5f, -X[W + j]);
    }
  }
  if (MS & 4) {
    pin(X, 24); pin(Z, 24);
    wg_fence();
  }
  if (PAR == 1) load_bias(b, c);
  if (MS & 4) {
#pragma unroll
    for (int k = 0; k < 6; k++) {
      wgmma_n48(A0, r.s0[k], dS + (D0 + k * KS + SA), 1);
      wgmma_n48(A1, r.s1[k], dS + (D1 + k * KS + SA), 1);
      if (k == 2 && NEXT) { confirm(ok, c.full + PAR * 8, c.row >> 1); wg_fence(); }
    }
    wg_commit();
  } else if (NEXT) {
    confirm(ok, c.full + PAR * 8, c.row >> 1);
  }
  pin(X + I, 24); pin(Z + I, 24);
#pragma unroll
  for (int j = 0; j < 24; j++) {
    if (PAR == 0) {
      Z[I + j] = fmaf(X[I + j], 0.5f, Z[I + j]); X[I + j] -= Z[I + j];
    } else {
      X[I + j] += Z[I + j]; Z[I + j] = fmaf(X[I + j], -0.5f, Z[I + j]);
      X[I + j] = fmaf(b[(j >> 2) * 2 + (j & 1)], 2.0f, X[I + j]);
    }
  }
  pin(X + I, 24); pin(Z + I, 24);
  if (MS & 1) {
    pin(t, 24);
#pragma unroll
    for (int j = 0; j < 24; j++) {
      if (PAR == 0) Z[W + j] = t[j] + __uint_as_float(c.never);
      else X[W + j] = fmaf(b[(j >> 2) * 2 + (j & 1)], 2.0f, t[j]);
    }
    pin(X + W, 24); pin(Z + W, 24);
  }
  wg_fence();
#pragma unroll
  for (int k = 0; k < 3; k++) {
    mma_pair<SLO, SHI, 48>(A0, r.s0[k], dS + (D0 + k * KS + SP));
    mma_pair<SLO, SHI, 48>(A1, r.s1[k], dS + (D1 + k * KS + SP));
  }
  wg_commit();
  if (NEXT) load_frag(r.d0, c, c.o0, 0);
  if (MS & 4) {
    stage_wait(c);
    wg_wait<1>();
    pin(X, 24); pin(Z, 24);
    store_part<PAR>(X, Z, c, 0, ES);
  }
  wg_fence();
#pragma unroll
  for (int k = 3; k < 6; k++) {
    mma_pair<SLO, SHI, 48>(A0, r.s0[k], dS + (D0 + k * KS + SP));
    mma_pair<SLO, SHI, 48>(A1, r.s1[k], dS + (D1 + k * KS + SP));
  }
  wg_commit();
  if (MS & 4) {
    confirm(c.live, c.full, 0);
    pin(X + 4 * ES, 24 - 4 * ES); pin(Z + 4 * ES, 24 - 4 * ES);
    store_part<PAR>(X, Z, c, ES, 6);
    stage_post(c);
  }
  if (MS == 3) mbar_wait(c.wready, 0);
}

template <int PAR, int MF>
__device__ __forceinline__ void first_half(Regs& r, Ctx& c) {
  constexpr uint32_t D0 = ((PAR ? 1 : 0) * U_POS) >> 4, D1 = ((PAR ? 2 : 3) * U_POS) >> 4;
  constexpr uint32_t KS = 256 >> 4;
  constexpr uint32_t FA = (PAR ? 2 * U_TAP : 0) >> 4, FP = (PAR ? 0 : U_TAP) >> 4;
  constexpr int FLO = MF & (PAR ? 4 : 2), FHI = MF & (PAR ? 2 : 4);
  constexpr bool TK = MF != 3 || PAR == 1;
  float* A0 = PAR ? r.X : r.Z;
  float* A1 = PAR ? r.Z : r.X;
  constexpr bool DEEP = MF == 3;
  uint32_t d1[12], dd[4][12], ok = 0;
  const uint64_t dF = refresh(c.desc, c);
  load_frag(d1, c, c.o0, 1);
  if (DEEP) { load_frag(dd[0], c, c.o1, 0); load_frag(dd[1], c, c.o1, 1); }
#pragma unroll
  for (int k = 0; k < 6; k++) {
    uint32_t ft0[4], ft1[4];
    uint32_t* f0 = k >= 4 ? r.fl[2 * (5 - k)] : ft0;
    uint32_t* f1 = k >= 4 ? r.fl[2 * (5 - k) + 1] : ft1;
    uint32_t* d = DEEP && k > 1 ? dd[k - 2] : (k & 1) ? d1 : r.d0;
    if (k == 0) ok = peek(c.full + 16 + PAR * 8, c.row >> 1);
    if (k == (DEEP ? 3 : 2)) confirm(ok, c.full + 16 + PAR * 8, c.row >> 1);
    if (k == 3 && DEEP) { load_frag(dd[2], c, c.o2, 0); load_frag(dd[3], c, c.o2, 1); }
    wg_wait<1>();
    if (PAR) transform(d, r.s0[k], f0, f1, r.s1[k]);
    else transform(d, f0, r.s0[k], r.s1[k], f1);
    const int keep = k > 0 ? 1 : MF == 7 ? c.never : 0;
    if (TK && k == 0) token_wait(c);
    wg_fence();
    mma_pair<FLO, FHI, 24>(A0, f0, dF + (D0 + k * KS + FP));
    if (MF & 1) wgmma_n48(A0, f0, dF + (D0 + k * KS + FA), keep);
    mma_pair<FLO, FHI, 24>(A1, f1, dF + (D1 + k * KS + FP));
    if (MF & 1) wgmma_n48(A1, f1, dF + (D1 + k * KS + FA), keep);
    wg_commit();
    if (k < 4 && !DEEP) load_frag(d, c, k < 2 ? c.o1 : c.o2, k & 1);
    if (k != 5 || MF == 3) bound8(r.s0[k], r.s1[k], c);
    if (k == 1) release(c, PAR * 8);
    if (k == 5 && (MF & 1)) release(c, 16 + PAR * 8);
  }
  if (TK) token_pass(c);
}

template <bool FIRST>
__device__ __forceinline__ void solo_row(Regs& r, Ctx& c, uint32_t par8) {
  constexpr uint32_t KS = 256 >> 4, PS = U_POS >> 4;
  constexpr uint32_t TY = (FIRST ? 0 : 2 * U_TAP) >> 4, TM = (FIRST ? 2 * U_TAP : 0) >> 4;
  uint32_t d[5][12];
  const uint64_t dF = refresh(c.desc, c);
  load_frag(d[0], c, c.o0, 1);
  const uint32_t ok = peek(c.full + 16 + par8, c.row >> 1);
  if (!FIRST) token_wait(c);
  load_frag(d[1], c, c.o1, 0);
  load_frag(d[2], c, c.o1, 1);
#pragma unroll
  for (int k = 0; k < 6; k++) {
    uint32_t v0[4], v1[4], v2[4], v3[4];
    if (k == 2) {
      if (FIRST) release(c, par8);
      confirm(ok, c.full + 16 + par8, c.row >> 1);
      load_frag(d[3], c, c.o2, 0);
      load_frag(d[4], c, c.o2, 1);
      if (!FIRST) token_pass(c);
    }
    if (k > 0 || !FIRST) wg_wait<1>();
    transform(k ? d[k - 1] : r.d0, v0, v1, v2, v3);
    wg_fence();
    wgmma_n48(r.X, v1, dF + (1 * PS + k * KS + TM), k > 0);
    wgmma_n48(r.Z, v2, dF + (2 * PS + k * KS + TM), k > 0);
    wgmma_n48(r.Z + 48, v0, dF + (0 * PS + k * KS + TY), k > 0 || !FIRST);
    wgmma_n48(r.X + 48, v3, dF + (3 * PS + k * KS + TY), k > 0 || !FIRST);
    wg_commit();
  }
  if (FIRST) release(c, 16 + par8);
}

__device__ __forceinline__ void tma_chunk(uint32_t dst, const CUtensorMap* tm, int ch, int xq, int y, uint32_t bar) {
  asm volatile(
      "{\n.reg .pred p;\nelect.sync _|p, 0xffffffff;\n"
      "@p mbarrier.arrive.expect_tx.shared::cta.b64 _, [%6], %9;\n"
      "@p mbarrier.arrive.expect_tx.shared::cluster.b64 _, [%8], %9;\n"
      "@p cp.async.bulk.tensor.4d.shared::cluster.global.mbarrier::complete_tx::bytes.multicast::cluster "
      "[%0], [%1, {%2, %3, %4, %5}], [%6], %7;\n}\n"
      ::"r"(dst), "l"(tm), "r"(ch), "r"(xq), "r"(0), "r"(y), "r"(bar), "h"((uint16_t)3), "r"(bar ^ (1u << 24)), "n"(CHUNK)
      : "memory");
}
__device__ __forceinline__ uint32_t u_block(int pos, int ky) {
  return pos * U_POS + (pos == 0 || pos == 3 ? ky : 2 - ky) * U_TAP;
}
__device__ __forceinline__ uint32_t raw_zone(int ky, int pc) {
  return pc < 4 ? u_block(pc, ky) : OFF_STAGE + (2 * ky + pc - 8) * U_TAP;
}
__device__ __forceinline__ void load_raw(uint32_t sb, const __nv_bfloat16* w, int ky, int up) {
#pragma unroll
  for (int pc = 0; pc < 6; pc++)
    asm volatile("{\n.reg .pred p;\nelect.sync _|p, 0xffffffff;\n"
                 "@p cp.async.bulk.shared::cluster.global.mbarrier::complete_tx::bytes [%0], [%1], %2, [%3];\n}\n"
                 ::"r"(sb + raw_zone(ky, pc)), "l"(w + ((up ? 2 - ky : ky) * 6 + pc) * 48 * 96), "n"(U_TAP),
                   "r"(sb + OFF_BAR + B_RAW + ky * 8) : "memory");
}
__device__ __forceinline__ void prefetch_l2(const void* p, uint32_t bytes) {
  asm volatile("{\n.reg .pred p;\nelect.sync _|p, 0xffffffff;\n@p cp.async.bulk.prefetch.L2.global [%0], %1;\n}\n"
               ::"l"(p), "r"(bytes) : "memory");
}
__device__ __forceinline__ void prefetch_row(const __nv_bfloat16* x, int strip, int y) {
  const int x0 = max(strip * 128 - 4, 0), x1 = min(strip * 128 + 132, IMG);
  if (y >= 0 && y < IMG) prefetch_l2(x + ((size_t)y * IMG + x0) * CH, (x1 - x0) * CH * 2);
}

__device__ __forceinline__ void bar_init(uint32_t bar, uint32_t count) {
  asm volatile("mbarrier.init.shared::cta.b64 [%0], %1;" ::"r"(bar), "r"(count) : "memory");
}
__device__ __forceinline__ void wino_w(uint32_t g0, uint32_t g1, uint32_t g2, uint32_t& u1, uint32_t& u2) {
  const float sl = bf_lo(g0) + bf_lo(g2), sh = bf_hi(g0) + bf_hi(g2);
  u1 = pack2(sl + bf_lo(g1), sh + bf_hi(g1));
  u2 = pack2((sl - bf_lo(g1)) * 0.5f, (sh - bf_hi(g1)) * 0.5f);
}
__device__ __forceinline__ void sts128(uint32_t a, uint4 v) {
  asm volatile("st.shared.v4.u32 [%0], {%1,%2,%3,%4};" ::"r"(a), "r"(v.x), "r"(v.y), "r"(v.z), "r"(v.w) : "memory");
}
__device__ __forceinline__ uint4 lds128(uint32_t a) {
  uint4 v;
  asm volatile("ld.shared.v4.u32 {%0,%1,%2,%3}, [%4];" : "=r"(v.x), "=r"(v.y), "=r"(v.z), "=r"(v.w) : "r"(a) : "memory");
  return v;
}

__global__ void __cluster_dims__(2, 1, 1) __launch_bounds__(384, 1)
conv_wino_kernel(const __grid_constant__ CUtensorMap tmx, const __grid_constant__ CUtensorMap tmo,
                 const __nv_bfloat16* __restrict__ x, const __nv_bfloat16* __restrict__ w,
                 const __nv_bfloat16* __restrict__ bias, uint64_t zero64, uint32_t never) {
  extern __shared__ __align__(1024) uint8_t smem_raw[];
  const uint32_t sb = (uint32_t)__cvta_generic_to_shared(smem_raw);
  if (sb != SMEM_BASE + ((blockIdx.x & 1) << 24)) __trap();
  const int tid = threadIdx.x, lane = tid & 31;
  const int warp = __shfl_sync(0xffffffff, tid >> 5, 0);
  const uint32_t rank = blockIdx.x & 1;
  const int cl = ((blockIdx.x >> 1) + 30) % 66;
  const uint32_t bars = sb + OFF_BAR;
  const int up = (cl >> 1) & 1, dir = 1 - 2 * up;

  if (warp == 8) {
    if (lane == 0) {
#pragma unroll
      for (int i = 0; i < 3; i++) bar_init(bars + B_RAW + i * 8, 1);
#pragma unroll
      for (int i = 0; i < 3; i++)
        asm volatile("mbarrier.arrive.expect_tx.shared::cta.b64 _, [%0], %1;" ::"r"(bars + B_RAW + i * 8), "n"(6 * U_TAP) : "memory");
    }
  } else if (warp == 9) {
    if (lane == 0) {
      asm volatile("prefetch.tensormap [%0];" ::"l"(&tmx) : "memory");
#pragma unroll
      for (int i = 0; i < 8; i++) bar_init(bars + B_FULL + i * 8, (i & 2) ? 1 : 2);
#pragma unroll
      for (int i = 0; i < 5; i++) bar_init(bars + B_EMPTY + i * 8, 8);
      bar_init(bars + B_WRDY, 4); bar_init(bars + B_WRDY + 8, 5); bar_init(bars + B_WRDY + 16, 4);
    }
  } else if (warp == 10) {
    if (blockIdx.x < 108) prefetch_l2(w + blockIdx.x * 768, 1536);
  }
  asm volatile("fence.mbarrier_init.release.cluster;" ::: "memory");
  __syncwarp();
  asm volatile("barrier.cluster.arrive.relaxed.aligned;" ::: "memory");
  if (warp == 8) {
    asm volatile("fence.proxy.async.shared::cta;" ::: "memory");
#pragma unroll 1
    for (int ky = 0; ky < 3; ky++) load_raw(sb, w, ky, up);
  }
  asm volatile("barrier.cluster.wait.aligned;" ::: "memory");

  if (warp < 8) {
    const int wg = warp >> 2, wq = warp & 3;
    if (wg) asm volatile("bar.arrive 2, 256;" ::: "memory");
    {
      const int i = lane & 7;
      uint32_t src[5], dst[5];
#pragma unroll
      for (int it = 0; it < 5; it++) {
        const int q = (wq + 4 * it) * 4 + (lane >> 3), rg = q / 6, j = (q + (i >> 1)) % 6;
        src[it] = sb + ((rg % 6) * 8 + i) * 192 + rank * 96 + j * 16;
        dst[it] = sb + j * 1536 + rg * 128 + i * 16;
        asm volatile("" : "+r"(src[it]), "+r"(dst[it]));
      }
#pragma unroll 1
      for (int ky = wg; ky <= 2 * wg; ky++) {
        uint4 g[5][3];
        mbar_wait(bars + B_RAW + ky * 8, 0);
#pragma unroll
        for (int it = 0; it < 5; it++) {
          if (it < 4 || wq < 2) {
            const bool lower = it < 2 || (it == 2 && wq == 0);
#pragma unroll
            for (int kx = 0; kx < 3; kx++) g[it][kx] = lds128(src[it] + (lower ? raw_zone(ky, 2 * kx) : raw_zone(ky, 2 * kx + 1)));
          }
        }
        if (ky == 0) asm volatile("bar.arrive 11, 256;" ::: "memory");
        asm volatile("bar.sync %0, %1;" ::"r"(ky == 0 ? 1 : ky == 1 ? 11 : 5), "r"(ky == 1 ? 256 : 128) : "memory");
        if (ky == 1 && lane == 0)
          asm volatile("mbarrier.arrive.shared::cluster.b64 _, [%0];" ::"r"((bars + B_HAND) | (1u << 24)) : "memory");
        __syncwarp();
#pragma unroll
        for (int it = 0; it < 5; it++) {
          if (it < 4 || wq < 2) {
            uint4 u1, u2;
            wino_w(g[it][0].x, g[it][1].x, g[it][2].x, u1.x, u2.x);
            wino_w(g[it][0].y, g[it][1].y, g[it][2].y, u1.y, u2.y);
            wino_w(g[it][0].z, g[it][1].z, g[it][2].z, u1.z, u2.z);
            wino_w(g[it][0].w, g[it][1].w, g[it][2].w, u1.w, u2.w);
            sts128(dst[it] + u_block(0, ky), g[it][0]);
            sts128(dst[it] + u_block(3, ky), g[it][2]);
            sts128(dst[it] + u_block(1, ky), u1);
            sts128(dst[it] + u_block(2, ky), u2);
          }
        }
        asm volatile("fence.proxy.async.shared::cta;" ::: "memory");
        __syncwarp();
        if (lane == 0) asm volatile("mbarrier.arrive.shared::cta.b64 _, [%0];" ::"r"(bars + B_WRDY + ky * 8) : "memory");
        __syncwarp();
      }
      mbar_wait(bars + B_WRDY, 0);
    }
    asm volatile("setmaxnreg.inc.sync.aligned.u32 240;");
    Ctx c;
#pragma unroll
    for (int m = 0; m < 2; m++) {
      const int hi = lane >> 4, h = (lane >> 3) & 1, gg = lane & 7;
      const int xr = m == 0 ? hi : 3 - 3 * hi, xq = 8 * wq + gg + (m == 0 ? 1 : 2 * hi);
      const uint32_t ad = sb + OFF_RING + NSLOT * wg * CHUNK + xr * PLANE + xq * 64;
      c.a[2 * m] = ad + ((h ^ ((ad >> 7) & 3)) << 4);
      c.a[2 * m + 1] = c.a[2 * m] ^ 32;
      asm volatile("" : "+r"(c.a[2 * m]), "+r"(c.a[2 * m + 1]));
    }
    c.stg = sb + OFF_STAGE + wg * STAGE + ((lane >> 3) * 32 + wq * 8 + (lane & 7)) * 128 + (lane & 7) * 16;
    c.lead = lane == 0;
    c.never = never;
    c.zero64 = zero64;
    c.desc = DESC_U;
    c.bias = sb + OFF_BIAS;
    c.full = bars + B_FULL + wg * 32;
    c.empty = SMEM_BASE + OFF_BAR + B_EMPTY + ((uint32_t)wg << 24);
    c.wready = bars + B_WRDY + 16;
    c.o0 = 0; c.o1 = CHUNK; c.o2 = 2 * CHUNK; c.row = 0;
    c.wg1 = __any_sync(0xffffffff, tid & 128);
    c.live = __any_sync(0xffffffff, never == 0);
    const int odd = seg_rows(cl, wg) & 1;
    Regs r;
#pragma unroll
    for (int i = 0; i < 72; i++) { r.X[i] = 0.f; r.Z[i] = 0.f; }
    mbar_wait(c.full + (odd ^ 1) * 8, 0);
    load_frag(r.d0, c, c.o0, 0);
    solo_row<true>(r, c, (odd ^ 1) * 8);
    advance(c);
    mbar_wait(c.full + odd * 8, 0);
    load_frag(r.d0, c, c.o0, 0);
    mbar_wait(bars + B_WRDY + 8, 0);
    if (odd) {
      float b[12];
      load_bias(b, c);
      wg_wait<0>();
      pin(r.X, 24); pin(r.Z, 24); pin(r.X + 48, 24); pin(r.Z + 48, 24);
#pragma unroll
      for (int j = 0; j < 24; j++) {
        const float y0 = r.Z[48 + j], y1 = r.X[48 + j];
        r.X[24 + j] = fmaf(b[(j >> 2) * 2 + (j & 1)], 2.0f, r.X[j]) + (y0 + y1);
        r.Z[24 + j] = fmaf(y0 - y1, 0.5f, r.Z[j]);
      }
      pin(r.X + 24, 24); pin(r.Z + 24, 24);
      first_half<1, 3>(r, c);
      wg_wait<0>();
      pin(r.X, 48); pin(r.Z, 48);
    } else {
      wg_wait<0>();
      pin(r.X, 24); pin(r.Z, 24); pin(r.X + 48, 24); pin(r.Z + 48, 24);
#pragma unroll
      for (int j = 0; j < 24; j++) {
        r.Z[24 + j] = fmaf(r.X[j], 0.5f, r.Z[48 + j]) + r.Z[j];
        r.X[24 + j] = fmaf(r.X[j], 0.5f, r.X[48 + j]) - r.Z[j];
      }
      pin(r.X + 24, 24); pin(r.Z + 24, 24);
      first_half<0, 3>(r, c);
      wg_wait<0>();
      pin(r.X, 48); pin(r.Z, 48);
    }
#pragma unroll
    for (int j = 24; j < 48; j++) { r.X[j + 24] = r.X[j] + __uint_as_float(never); r.Z[j + 24] = r.Z[j] + __uint_as_float(never); }
    pin(r.X + 48, 24); pin(r.Z + 48, 24);
    int code = 1 + odd, rem = 7;
  head:
    if (__builtin_expect(code != 0, 0)) {
      if (code == 1) {
        code = never;
        second_half<1, 3>(r, c);
        goto odd_first;
      }
      code = never;
      second_half<0, 3>(r, c);
      goto even_first;
    }
    second_half<1, 7>(r, c);
    if (__builtin_expect(rem == 0, 0)) goto tail;
  odd_first:
    first_half<1, 7>(r, c);
    if (__builtin_expect(code != 0, 0)) goto head;
    second_half<0, 7>(r, c);
  even_first:
    first_half<0, 7>(r, c);
    rem--;
    goto head;
  tail:
    first_half<1, 6>(r, c);
    if (cl < 64) {
      second_half<0, 6>(r, c);
      solo_row<false>(r, c, 0);
      stage_wait(c);
      wg_wait<0>();
      pin(r.X, 24); pin(r.Z, 24); pin(r.X + 48, 24); pin(r.Z + 48, 24);
#pragma unroll
      for (int j = 0; j < 6; j++) {
        float y0[4], y1[4];
#pragma unroll
        for (int e = 0; e < 4; e++) {
          const float xm = r.X[4 * j + e], zm = r.Z[4 * j + e];
          y0[e] = fmaf(xm, 0.5f, r.Z[48 + 4 * j + e]) + zm;
          y1[e] = fmaf(xm, 0.5f, r.X[48 + 4 * j + e]) - zm;
        }
        stage_cols(c, j, y0, y1);
      }
      stage_post(c);
    } else {
      second_half<0, 6, false>(r, c);
      wg_wait<0>();
      pin(r.X + 48, 24); pin(r.Z + 48, 24);
      c.stg += alt_stage(wg) - (OFF_STAGE + wg * STAGE);
      store_part<0>(r.X + 48, r.Z + 48, c, 0, 6);
      WG_BAR("arrive", 12, 13, 160);
    }
    if (wg == 0) token_wait(c);
  } else {
    asm volatile("setmaxnreg.dec.sync.aligned.u32 24;");
    if (warp == 8) asm volatile("bar.arrive 6, 64;" ::: "memory");
    if (warp == 10) {
      if (rank == 1) prefetch_row(x, seg_strip(cl, 0), seg_y0(cl, 0) - 1 + 17 * up);
      if (lane < 24) {
        const uint32_t v = *reinterpret_cast<const uint32_t*>(bias + rank * 48 + 2 * lane);
        asm volatile("st.shared.v2.f32 [%0], {%1, %2};" ::"r"(sb + OFF_BIAS + ((lane + 2) & 3) * 64 + (lane >> 2) * 8),
                     "f"(bf_lo(v)), "f"(bf_hi(v)) : "memory");
      }
      __syncwarp();
      if (lane == 0) asm volatile("mbarrier.arrive.shared::cta.b64 _, [%0];" ::"r"(bars + B_WRDY + 8) : "memory");
      __syncwarp();
    }
    if (warp >= 10) {
      const int wg = warp - 10, nrows = seg_rows(cl, wg), y0 = seg_y0(cl, wg) + (nrows - 1) * up;
#pragma unroll 1
      for (int i = 0; i < nrows; i++) {
        const bool alt = cl >= 64 && i == nrows - 1;
        if (!alt) {
          asm volatile("cp.async.bulk.wait_group.read 0;" ::: "memory");
          __syncwarp();
          asm volatile("bar.arrive %0, 160;" ::"r"(8 + wg) : "memory");
        }
        asm volatile("bar.sync %0, 160;" ::"r"((alt ? 12 : 14) + wg) : "memory");
        asm volatile("fence.proxy.async.shared::cta;" ::: "memory");
        asm volatile(
            "{\n.reg .pred p;\nelect.sync _|p, 0xffffffff;\n"
            "@p cp.async.bulk.tensor.5d.global.shared::cta.bulk_group [%0, {%1, %2, %3, %1, %4}], [%5];\n}\n"
            ::"l"(&tmo), "r"(0), "r"(rank), "r"(seg_strip(cl, wg) * 32), "r"(y0 + dir * i),
              "r"(sb + (alt ? alt_stage(wg) : OFF_STAGE + wg * STAGE)) : "memory");
        asm volatile("cp.async.bulk.commit_group;" ::: "memory");
      }
      asm volatile("cp.async.bulk.wait_group.read 0;" ::: "memory");
    }
    if (warp == 9) {
      const int strip = seg_strip(cl, rank), nin = seg_rows(cl, rank) + 2;
      int y = seg_y0(cl, rank) - 1 + (nin - 1) * up;
      uint32_t slot = 0, par8 = ((nin & 1) ^ 1) * 8;
      asm volatile("bar.sync 6, 64;" ::: "memory");
      if (rank) {
        prefetch_row(x, strip, y);
        mbar_wait(bars + B_HAND, 0);
      }
#pragma unroll 1
      for (int i = 0; i < nin; i++, y += dir, par8 ^= 8) {
        if (i >= PF_FROM && i + 1 < nin) prefetch_row(x, strip, y + dir);
#pragma unroll 1
        for (int ch = 0; ch < 3; ch++) {
          if (ch == 0 && i >= 2) mbar_wait(bars + B_EMPTY + 16 + par8, (i - 2) >> 1);
          if (ch == 2 && i >= 1) mbar_wait(bars + B_EMPTY + (par8 ^ 8), (i - 1) >> 1);
          if (y < IMG)
            tma_chunk(sb + OFF_RING + NSLOT * rank * CHUNK + slot, &tmx, ch * 32, strip * 32 - 1, y,
                      bars + B_FULL + rank * 32 + (ch >> 1) * 16 + par8);
          slot = next_slot(slot);
        }
      }
    }
  }
}

typedef CUresult (*EncodeFn)(CUtensorMap*, CUtensorMapDataType, cuuint32_t, void*, const cuuint64_t*, const cuuint64_t*,
                             const cuuint32_t*, const cuuint32_t*, CUtensorMapInterleave, CUtensorMapSwizzle,
                             CUtensorMapL2promotion, CUtensorMapFloatOOBfill);

}

extern "C" void kernel_launch(void* const* d_in, const int* in_sizes, int n_in, void* d_out, int out_size) {
  (void)in_sizes; (void)n_in; (void)out_size;
  static EncodeFn encode = nullptr;
  if (!encode) {
    void* fn = nullptr;
    cudaDriverEntryPointQueryResult qr;
    cudaGetDriverEntryPoint("cuTensorMapEncodeTiled", &fn, cudaEnableDefault, &qr);
    encode = (EncodeFn)fn;
    cudaFuncSetAttribute(conv_wino_kernel, cudaFuncAttributeMaxDynamicSharedMemorySize, SMEM_BYTES);
  }
  CUtensorMap tmx, tmo;
  const cuuint32_t es[5] = {1, 1, 1, 1, 1};
  {
    const cuuint64_t dims[4] = {CH, IMG / 4, 4, IMG};
    const cuuint64_t strides[3] = {4 * CH * 2, CH * 2, (cuuint64_t)IMG * CH * 2};
    const cuuint32_t box[4] = {32, 34, 4, 1};
    encode(&tmx, CU_TENSOR_MAP_DATA_TYPE_BFLOAT16, 4, d_in[0], dims, strides, box, es, CU_TENSOR_MAP_INTERLEAVE_NONE,
           CU_TENSOR_MAP_SWIZZLE_64B, CU_TENSOR_MAP_L2_PROMOTION_L2_128B, CU_TENSOR_MAP_FLOAT_OOB_FILL_NONE);
  }
  {
    const cuuint64_t dims[5] = {48, 2, IMG / 4, 4, IMG};
    const cuuint64_t strides[4] = {96, 4 * CH * 2, CH * 2, (cuuint64_t)IMG * CH * 2};
    const cuuint32_t box[5] = {64, 1, 32, 4, 1};
    encode(&tmo, CU_TENSOR_MAP_DATA_TYPE_BFLOAT16, 5, d_out, dims, strides, box, es, CU_TENSOR_MAP_INTERLEAVE_NONE,
           CU_TENSOR_MAP_SWIZZLE_128B, CU_TENSOR_MAP_L2_PROMOTION_NONE, CU_TENSOR_MAP_FLOAT_OOB_FILL_NONE);
  }
  conv_wino_kernel<<<NCTA, 384, SMEM_BYTES>>>(tmx, tmo, (const __nv_bfloat16*)d_in[0], (const __nv_bfloat16*)d_in[1],
                                              (const __nv_bfloat16*)d_in[2], 0ull, 0u);
}
```
